```python
import torch

def _softmax(x, axis=-1):
    return torch.softmax(x, dim=axis)
def _gelu(x):
    return torch.nn.functional.gelu(x, approximate="tanh")
def _silu(x):
    return torch.nn.functional.silu(x)
def _sigmoid(x):
    return torch.sigmoid(x)
def _layernorm(x, axis=-1, eps=1e-5):
    m = x.mean(dim=axis, keepdim=True)
    v = x.var(dim=axis, keepdim=True, unbiased=False)
    return (x - m) / torch.sqrt(v + eps)
def _scatter_add(tgt, idx, src, axis=0):
    return tgt.clone().index_add_(axis, idx, src)
def _segment_sum(src, seg, n):
    out = torch.zeros((n,) + src.shape[1:], dtype=src.dtype)
    return out.index_add_(0, seg, src)
def _pad(x, pw):
    flat = tuple(v for pair in reversed(pw) for v in pair)
    return torch.nn.functional.pad(x, flat)

kernel_name = 'interleave_layers__softmax_full_mha__mixer_channel_mlp__prompt'

def setup_inputs():

    _w = (lambda a: (lambda t: t.to(torch.bfloat16) if t.is_floating_point() else t)(torch.as_tensor(a)))
    def _A_setup():
        B, S, D = 1, 2048, 640
        return {
            "x": _w((lambda *s: torch.randn(*s, dtype=torch.bfloat16) * 0.05)(B, S, D)),
            "wqkv": _w((lambda *s: torch.randn(*s, dtype=torch.bfloat16) * 0.05)(D, 3 * D)),
            "wo": _w((lambda *s: torch.randn(*s, dtype=torch.bfloat16) * 0.05)(D, D)),
        }
    _A_in = _A_setup()

    def _B_setup():
        B, S, D, F = 1, 2048, 640, 1728
        return {
            "x": _w((lambda *s: torch.randn(*s, dtype=torch.bfloat16) * 0.05)(B, S, D)),
            "w1": _w((lambda *s: torch.randn(*s, dtype=torch.bfloat16) * 3.2)(D, F) * (D ** -0.5)),
            "b1": _w((lambda *s: torch.randn(*s, dtype=torch.bfloat16) * 0.8)(F)),
            "w2": _w((lambda *s: torch.randn(*s, dtype=torch.bfloat16) * 0.2)(F, D) * (F ** -0.5)),
            "b2": _w((lambda *s: torch.randn(*s, dtype=torch.bfloat16) * 0.2)(D)),
        }
    _B_in = _B_setup()

    return {
        "A_x": _A_in["x"],
        "A_wqkv": _A_in["wqkv"],
        "A_wo": _A_in["wo"],
        "B_x": _B_in["x"],
        "B_w1": _B_in["w1"],
        "B_b1": _B_in["b1"],
        "B_w2": _B_in["w2"],
        "B_b2": _B_in["b2"],
    }

def reference(A_x, A_wqkv, A_wo, B_x, B_w1, B_b1, B_w2, B_b2):
    def _A_ref(x, wqkv, wo):
        B, S, D = x.shape
        H = 32; Dh = D // H
        qkv = (lambda x, *d: x.permute(*d))((x @ wqkv).reshape(B, S, 3, H, Dh), 2, 0, 3, 1, 4)
        q, k, v = qkv[0], qkv[1], qkv[2]
        scale = Dh ** -0.5
        scores = torch.einsum("bhqd,bhkd->bhqk", q, k) * scale
        p = _softmax(scores, axis=-1)
        o = torch.einsum("bhqk,bhkd->bhqd", p, v)
        return (lambda x, *d: x.permute(*d))(o, 0, 2, 1, 3).reshape(B, S, D) @ wo

    def _B_ref(x, w1, b1, w2, b2):
        y = _layernorm(x, axis=-1)
        h = _gelu(torch.einsum("bsd,df->bsf", y, w1) + b1)
        return torch.einsum("bsf,fd->bsd", h, w2) + b2

    x = A_x
    x = x + _A_ref(_layernorm(x, axis=-1), A_wqkv, A_wo)
    x = x + _B_ref(_layernorm(x, axis=-1), B_w1, B_b1, B_w2, B_b2)
    x = x + _A_ref(_layernorm(x, axis=-1), A_wqkv, A_wo)
    x = x + _B_ref(_layernorm(x, axis=-1), B_w1, B_b1, B_w2, B_b2)
    return x
```

```cpp
#include <cuda_runtime.h>
#include <cuda_bf16.h>
#include <cuda.h>
#include <stdint.h>

namespace {

typedef __nv_bfloat16 bf16;
typedef unsigned char u8;

constexpr int SEQ = 2048, DM = 640, FF = 1728, NQKV = 1920;
constexpr float LN_EPS = 1e-5f;

__device__ __align__(1024) bf16 g_x[2][SEQ * DM];
__device__ __align__(1024) bf16 g_o[SEQ * DM];
__device__ __align__(1024) bf16 g_qkv[96 * SEQ * 24];
#define g_h g_qkv
__device__ __align__(1024) bf16 g_wqkv[DM * NQKV];
__device__ __align__(1024) bf16 g_wo[DM * DM];
__device__ __align__(1024) bf16 g_w1[DM * FF];
__device__ __align__(1024) bf16 g_w2[FF * DM];
__device__ __align__(16) float g_cs_qkv[20 * NQKV];
__device__ __align__(16) float g_cs_w1[10 * FF];
__device__ __align__(16) float2 g_stats[SEQ * 8];
__device__ __align__(16) float g_nmax[64 * 128];

__device__ __forceinline__ uint32_t smem_u32(const void* p) { return (uint32_t)__cvta_generic_to_shared(p); }
__device__ __forceinline__ uint64_t mkdesc(uint32_t addr, uint32_t lbo, uint32_t sbo) {
  return (uint64_t)((addr & 0x3FFFF) >> 4) | ((uint64_t)(lbo >> 4) << 16) | ((uint64_t)(sbo >> 4) << 32);
}
__device__ __forceinline__ void mbar_init(uint32_t bar, uint32_t cnt) { asm volatile("mbarrier.init.shared::cta.b64 [%0], %1;" ::"r"(bar), "r"(cnt)); }
__device__ __forceinline__ void mbar_expect_tx(uint32_t bar, uint32_t bytes) { asm volatile("mbarrier.arrive.expect_tx.shared::cta.b64 _, [%0], %1;" ::"r"(bar), "r"(bytes) : "memory"); }
__device__ __forceinline__ void mbar_arrive(uint32_t bar) { asm volatile("mbarrier.arrive.shared::cta.b64 _, [%0];" ::"r"(bar) : "memory"); }
__device__ __forceinline__ void mbar_wait(uint32_t bar, uint32_t parity) {
  asm volatile(
      "{\n.reg .pred p;\n.reg .u32 c;\nmov.u32 c, 0;\n"
      "LAB_WAIT:\n"
      "mbarrier.try_wait.parity.shared::cta.b64 p, [%0], %1;\n"
      "@p bra LAB_DONE;\n"
      "add.u32 c, c, 1;\n"
      "setp.lt.u32 p, c, 4000000;\n"
      "@p bra LAB_WAIT;\n"
      "trap;\n"
      "LAB_DONE:\n}\n" ::"r"(bar), "r"(parity) : "memory");
}
__device__ __forceinline__ void bulk_g2s(uint32_t dst, const void* src, uint32_t bytes, uint32_t bar) {
  asm volatile("cp.async.bulk.shared::cluster.global.mbarrier::complete_tx::bytes [%0], [%1], %2, [%3];" ::"r"(dst), "l"(src), "r"(bytes), "r"(bar) : "memory");
}
__device__ __forceinline__ void bulk_g2s_ef(uint32_t dst, const void* src, uint32_t bytes, uint32_t bar) {
  uint64_t pol; asm("createpolicy.fractional.L2::evict_first.b64 %0, 1.0;" : "=l"(pol));
  asm volatile("cp.async.bulk.shared::cluster.global.mbarrier::complete_tx::bytes.L2::cache_hint [%0], [%1], %2, [%3], %4;" ::"r"(dst), "l"(src), "r"(bytes), "r"(bar), "l"(pol) : "memory");
}
__device__ __forceinline__ void tma_4d(uint32_t dst, const CUtensorMap* m, int c2, int c3, uint32_t bar) {
  uint64_t pol; asm("createpolicy.fractional.L2::evict_first.b64 %0, 1.0;" : "=l"(pol));
  asm volatile("cp.async.bulk.tensor.4d.shared::cluster.global.mbarrier::complete_tx::bytes.L2::cache_hint [%0], [%1, {%3, %3, %4, %5}], [%2], %6;" ::"r"(dst), "l"(m), "r"(bar), "r"(0), "r"(c2), "r"(c3), "l"(pol) : "memory");
}
__device__ __forceinline__ void bulk_store(void* dst, uint32_t src, uint32_t bytes) {
  asm volatile("cp.async.bulk.global.shared::cta.bulk_group [%0], [%1], %2;" ::"l"(dst), "r"(src), "r"(bytes) : "memory");
}
__device__ __forceinline__ void pdl_wait() { asm volatile("griddepcontrol.wait;" ::: "memory"); }
__device__ __forceinline__ void pdl_launch() { asm volatile("griddepcontrol.launch_dependents;" ::: "memory"); }
#define WG_FENCE asm volatile("wgmma.fence.sync.aligned;" ::: "memory")
#define WG_COMMIT asm volatile("wgmma.commit_group.sync.aligned;" ::: "memory")
#define WG_WAIT(n) asm volatile("wgmma.wait_group.sync.aligned " #n ";" ::: "memory")
template <int N> __device__ __forceinline__ void fence_regs(float (&d)[N]) {
#pragma unroll
  for (int i = 0; i < N; i++) asm volatile("" : "+f"(d[i])::"memory");
}
__device__ __forceinline__ float ex2(float x) { float y; asm("ex2.approx.ftz.f32 %0, %1;" : "=f"(y) : "f"(x)); return y; }
__device__ __forceinline__ float tanh_fast(float x) { float y; asm("tanh.approx.f32 %0, %1;" : "=f"(y) : "f"(x)); return y; }
__device__ __forceinline__ float sqrt_fast(float x) { float y; asm("sqrt.approx.f32 %0, %1;" : "=f"(y) : "f"(x)); return y; }
__device__ __forceinline__ uint32_t pack2(float lo, float hi) { uint32_t r; asm("cvt.rn.bf16x2.f32 %0, %1, %2;" : "=r"(r) : "f"(hi), "f"(lo)); return r; }
__device__ __forceinline__ uint64_t policy_stream() { uint64_t p; asm("createpolicy.fractional.L2::evict_first.b64 %0, 1.0;" : "=l"(p)); return p; }
__device__ __forceinline__ uint4 ld_stream(const uint4* p, uint64_t pol) {
  uint4 v; asm("ld.global.nc.L2::cache_hint.v4.u32 {%0,%1,%2,%3}, [%4], %5;" : "=r"(v.x), "=r"(v.y), "=r"(v.z), "=r"(v.w) : "l"(p), "l"(pol)); return v;
}
template <typename T> __device__ __forceinline__ T ldg(const void* p) { return *reinterpret_cast<const T*>(p); }
__device__ __forceinline__ float bflo(uint32_t v) { return __uint_as_float(v << 16); }
__device__ __forceinline__ float bfhi(uint32_t v) { return __uint_as_float(v & 0xFFFF0000u); }

template<int TB> __device__ __forceinline__ void wgmma_rs_n64(float (&d)[32], uint32_t a0, uint32_t a1, uint32_t a2, uint32_t a3, uint64_t db) {
  asm volatile("wgmma.mma_async.sync.aligned.m64n64k16.f32.bf16.bf16 {%0,%1,%2,%3,%4,%5,%6,%7,%8,%9,%10,%11,%12,%13,%14,%15,%16,%17,%18,%19,%20,%21,%22,%23,%24,%25,%26,%27,%28,%29,%30,%31}, {%32,%33,%34,%35}, %36, 1, 1, 1, %37;"
    : "+f"(d[0]),"+f"(d[1]),"+f"(d[2]),"+f"(d[3]),"+f"(d[4]),"+f"(d[5]),"+f"(d[6]),"+f"(d[7]),"+f"(d[8]),"+f"(d[9]),"+f"(d[10]),"+f"(d[11]),"+f"(d[12]),"+f"(d[13]),"+f"(d[14]),"+f"(d[15]),"+f"(d[16]),"+f"(d[17]),"+f"(d[18]),"+f"(d[19]),"+f"(d[20]),"+f"(d[21]),"+f"(d[22]),"+f"(d[23]),"+f"(d[24]),"+f"(d[25]),"+f"(d[26]),"+f"(d[27]),"+f"(d[28]),"+f"(d[29]),"+f"(d[30]),"+f"(d[31])
    : "r"(a0), "r"(a1), "r"(a2), "r"(a3), "l"(db), "n"(TB));
}
template<int TB> __device__ __forceinline__ void wgmma_rs_n64_z(float (&d)[32], uint32_t a0, uint32_t a1, uint32_t a2, uint32_t a3, uint64_t db) {
  asm volatile("wgmma.mma_async.sync.aligned.m64n64k16.f32.bf16.bf16 {%0,%1,%2,%3,%4,%5,%6,%7,%8,%9,%10,%11,%12,%13,%14,%15,%16,%17,%18,%19,%20,%21,%22,%23,%24,%25,%26,%27,%28,%29,%30,%31}, {%32,%33,%34,%35}, %36, 0, 1, 1, %37;"
    : "=f"(d[0]),"=f"(d[1]),"=f"(d[2]),"=f"(d[3]),"=f"(d[4]),"=f"(d[5]),"=f"(d[6]),"=f"(d[7]),"=f"(d[8]),"=f"(d[9]),"=f"(d[10]),"=f"(d[11]),"=f"(d[12]),"=f"(d[13]),"=f"(d[14]),"=f"(d[15]),"=f"(d[16]),"=f"(d[17]),"=f"(d[18]),"=f"(d[19]),"=f"(d[20]),"=f"(d[21]),"=f"(d[22]),"=f"(d[23]),"=f"(d[24]),"=f"(d[25]),"=f"(d[26]),"=f"(d[27]),"=f"(d[28]),"=f"(d[29]),"=f"(d[30]),"=f"(d[31])
    : "r"(a0), "r"(a1), "r"(a2), "r"(a3), "l"(db), "n"(TB));
}
template<int TB> __device__ __forceinline__ void wgmma_rs_n24(float (&d)[12], uint32_t a0, uint32_t a1, uint32_t a2, uint32_t a3, uint64_t db) {
  asm volatile("wgmma.mma_async.sync.aligned.m64n24k16.f32.bf16.bf16 {%0,%1,%2,%3,%4,%5,%6,%7,%8,%9,%10,%11}, {%12,%13,%14,%15}, %16, 1, 1, 1, %17;"
    : "+f"(d[0]),"+f"(d[1]),"+f"(d[2]),"+f"(d[3]),"+f"(d[4]),"+f"(d[5]),"+f"(d[6]),"+f"(d[7]),"+f"(d[8]),"+f"(d[9]),"+f"(d[10]),"+f"(d[11])
    : "r"(a0), "r"(a1), "r"(a2), "r"(a3), "l"(db), "n"(TB));
}
template<int TB> __device__ __forceinline__ void wgmma_rs_n24_z(float (&d)[12], uint32_t a0, uint32_t a1, uint32_t a2, uint32_t a3, uint64_t db) {
  asm volatile("wgmma.mma_async.sync.aligned.m64n24k16.f32.bf16.bf16 {%0,%1,%2,%3,%4,%5,%6,%7,%8,%9,%10,%11}, {%12,%13,%14,%15}, %16, 0, 1, 1, %17;"
    : "=f"(d[0]),"=f"(d[1]),"=f"(d[2]),"=f"(d[3]),"=f"(d[4]),"=f"(d[5]),"=f"(d[6]),"=f"(d[7]),"=f"(d[8]),"=f"(d[9]),"=f"(d[10]),"=f"(d[11])
    : "r"(a0), "r"(a1), "r"(a2), "r"(a3), "l"(db), "n"(TB));
}
template<int TB, int NA> __device__ __forceinline__ void wgmma_ss_n80(float (&d)[NA], uint64_t da, uint64_t db) {
  asm volatile("wgmma.mma_async.sync.aligned.m64n80k16.f32.bf16.bf16 {%0,%1,%2,%3,%4,%5,%6,%7,%8,%9,%10,%11,%12,%13,%14,%15,%16,%17,%18,%19,%20,%21,%22,%23,%24,%25,%26,%27,%28,%29,%30,%31,%32,%33,%34,%35,%36,%37,%38,%39}, %40, %41, 1, 1, 1, 0, %42;"
    : "+f"(d[0]),"+f"(d[1]),"+f"(d[2]),"+f"(d[3]),"+f"(d[4]),"+f"(d[5]),"+f"(d[6]),"+f"(d[7]),"+f"(d[8]),"+f"(d[9]),"+f"(d[10]),"+f"(d[11]),"+f"(d[12]),"+f"(d[13]),"+f"(d[14]),"+f"(d[15]),"+f"(d[16]),"+f"(d[17]),"+f"(d[18]),"+f"(d[19]),"+f"(d[20]),"+f"(d[21]),"+f"(d[22]),"+f"(d[23]),"+f"(d[24]),"+f"(d[25]),"+f"(d[26]),"+f"(d[27]),"+f"(d[28]),"+f"(d[29]),"+f"(d[30]),"+f"(d[31]),"+f"(d[32]),"+f"(d[33]),"+f"(d[34]),"+f"(d[35]),"+f"(d[36]),"+f"(d[37]),"+f"(d[38]),"+f"(d[39])
    : "l"(da), "l"(db), "n"(TB));
}
template<int TB, int NA> __device__ __forceinline__ void wgmma_ss_n96(float (&d)[NA], uint64_t da, uint64_t db) {
  asm volatile("wgmma.mma_async.sync.aligned.m64n96k16.f32.bf16.bf16 {%0,%1,%2,%3,%4,%5,%6,%7,%8,%9,%10,%11,%12,%13,%14,%15,%16,%17,%18,%19,%20,%21,%22,%23,%24,%25,%26,%27,%28,%29,%30,%31,%32,%33,%34,%35,%36,%37,%38,%39,%40,%41,%42,%43,%44,%45,%46,%47}, %48, %49, 1, 1, 1, 0, %50;"
    : "+f"(d[0]),"+f"(d[1]),"+f"(d[2]),"+f"(d[3]),"+f"(d[4]),"+f"(d[5]),"+f"(d[6]),"+f"(d[7]),"+f"(d[8]),"+f"(d[9]),"+f"(d[10]),"+f"(d[11]),"+f"(d[12]),"+f"(d[13]),"+f"(d[14]),"+f"(d[15]),"+f"(d[16]),"+f"(d[17]),"+f"(d[18]),"+f"(d[19]),"+f"(d[20]),"+f"(d[21]),"+f"(d[22]),"+f"(d[23]),"+f"(d[24]),"+f"(d[25]),"+f"(d[26]),"+f"(d[27]),"+f"(d[28]),"+f"(d[29]),"+f"(d[30]),"+f"(d[31]),"+f"(d[32]),"+f"(d[33]),"+f"(d[34]),"+f"(d[35]),"+f"(d[36]),"+f"(d[37]),"+f"(d[38]),"+f"(d[39]),"+f"(d[40]),"+f"(d[41]),"+f"(d[42]),"+f"(d[43]),"+f"(d[44]),"+f"(d[45]),"+f"(d[46]),"+f"(d[47])
    : "l"(da), "l"(db), "n"(TB));
}
template<int TB, int NA> __device__ __forceinline__ void wgmma_ss_n120(float (&d)[NA], uint64_t da, uint64_t db) {
  asm volatile("wgmma.mma_async.sync.aligned.m64n120k16.f32.bf16.bf16 {%0,%1,%2,%3,%4,%5,%6,%7,%8,%9,%10,%11,%12,%13,%14,%15,%16,%17,%18,%19,%20,%21,%22,%23,%24,%25,%26,%27,%28,%29,%30,%31,%32,%33,%34,%35,%36,%37,%38,%39,%40,%41,%42,%43,%44,%45,%46,%47,%48,%49,%50,%51,%52,%53,%54,%55,%56,%57,%58,%59}, %60, %61, 1, 1, 1, 0, %62;"
    : "+f"(d[0]),"+f"(d[1]),"+f"(d[2]),"+f"(d[3]),"+f"(d[4]),"+f"(d[5]),"+f"(d[6]),"+f"(d[7]),"+f"(d[8]),"+f"(d[9]),"+f"(d[10]),"+f"(d[11]),"+f"(d[12]),"+f"(d[13]),"+f"(d[14]),"+f"(d[15]),"+f"(d[16]),"+f"(d[17]),"+f"(d[18]),"+f"(d[19]),"+f"(d[20]),"+f"(d[21]),"+f"(d[22]),"+f"(d[23]),"+f"(d[24]),"+f"(d[25]),"+f"(d[26]),"+f"(d[27]),"+f"(d[28]),"+f"(d[29]),"+f"(d[30]),"+f"(d[31]),"+f"(d[32]),"+f"(d[33]),"+f"(d[34]),"+f"(d[35]),"+f"(d[36]),"+f"(d[37]),"+f"(d[38]),"+f"(d[39]),"+f"(d[40]),"+f"(d[41]),"+f"(d[42]),"+f"(d[43]),"+f"(d[44]),"+f"(d[45]),"+f"(d[46]),"+f"(d[47]),"+f"(d[48]),"+f"(d[49]),"+f"(d[50]),"+f"(d[51]),"+f"(d[52]),"+f"(d[53]),"+f"(d[54]),"+f"(d[55]),"+f"(d[56]),"+f"(d[57]),"+f"(d[58]),"+f"(d[59])
    : "l"(da), "l"(db), "n"(TB));
}

struct TileMap { unsigned char t[132]; int use; };
__device__ unsigned g_started[8];
__device__ __forceinline__ int tile_enter(const TileMap& m, int slot) {
  if (!m.use) return blockIdx.x;
  uint32_t sm; asm volatile("mov.u32 %0, %%smid;" : "=r"(sm));
  if (sm >= 132) __trap();
  if (threadIdx.x == 0) asm volatile("red.relaxed.gpu.global.add.u32 [%0], 1;" ::"l"(&g_started[slot]) : "memory");
  return m.t[sm];
}
__device__ __forceinline__ void tile_leave(const TileMap& m, int slot) {
  if (!m.use) return;
  for (int i = 0;; i++) {
    unsigned c; asm volatile("ld.relaxed.gpu.global.u32 %0, [%1];" : "=r"(c) : "l"(&g_started[slot]) : "memory");
    if (c >= 132) break;
    if (i > 2000000) __trap();
  }
}
constexpr int QG0 = 15, QG1 = 15;
constexpr int WG0 = 15, WG1 = 12;
constexpr int PREP_X = 512, PREP_QKV = 640;

__device__ __forceinline__ void retile_wqkv(const bf16* __restrict__ w, int item, u8* sm) {
  const uint64_t pol = policy_stream();
  const int tid = threadIdx.x, kb = item >> 3, cb = item & 7;
  uint4 v[8];
#pragma unroll
  for (int i = 0; i < 8; i++) {
    const int c = tid + 128 * i, r = c / 30, q = c - r * 30;
    if (c < 960) v[i] = ld_stream(reinterpret_cast<const uint4*>(w + (size_t)(kb * 32 + r) * NQKV + cb * 240) + q, pol);
  }
#pragma unroll
  for (int i = 0; i < 8; i++) {
    const int c = tid + 128 * i, r = c / 30, q = c - r * 30;
    if (c < 960) *reinterpret_cast<uint4*>(sm + r * 496 + q * 16) = v[i];
  }
  __syncthreads();
  const int kl = tid & 7;
#pragma unroll
  for (int i = 0; i < 2; i++) {
    const int g = (tid >> 3) + 16 * i;
    if (g < 30) {
      const int p = g / 5, j = g - p * 5;
      const int ua = j == 4 ? 4 : (j < 2 ? 2 * j : 2 * j + 1), ub = j == 4 ? 9 : ua + 1;
      const int sub = g / QG0, gl = g - sub * QG0;
      uint4* dst = reinterpret_cast<uint4*>(g_wqkv) + ((size_t)((cb * 2 + sub) * 80 + kb * 4) * QG0 + gl) * 8 + kl;
      float s[8];
#pragma unroll
      for (int e = 0; e < 8; e++) s[e] = 0.f;
#pragma unroll
      for (int o = 0; o < 4; o++) {
        const uint2 lo = *reinterpret_cast<const uint2*>(sm + (o * 8 + kl) * 496 + p * 80 + ua * 8), hi = *reinterpret_cast<const uint2*>(sm + (o * 8 + kl) * 496 + p * 80 + ub * 8);
        dst[o * QG0 * 8] = make_uint4(lo.x, lo.y, hi.x, hi.y);
        s[0] += bflo(lo.x); s[1] += bfhi(lo.x); s[2] += bflo(lo.y); s[3] += bfhi(lo.y);
        s[4] += bflo(hi.x); s[5] += bfhi(hi.x); s[6] += bflo(hi.y); s[7] += bfhi(hi.y);
      }
      const uint32_t mask = (i == 1 && tid >= 96) ? 0x0000ffffu : 0xffffffffu;
#pragma unroll
      for (int e = 0; e < 8; e++) {
        s[e] += __shfl_xor_sync(mask, s[e], 1);
        s[e] += __shfl_xor_sync(mask, s[e], 2);
        s[e] += __shfl_xor_sync(mask, s[e], 4);
      }
      if (kl == 0) {
        float4* d = reinterpret_cast<float4*>(g_cs_qkv + kb * NQKV + cb * 240 + g * 8);
        d[0] = make_float4(s[0], s[1], s[2], s[3]);
        d[1] = make_float4(s[4], s[5], s[6], s[7]);
      }
    }
  }
}

__global__ void __launch_bounds__(128) prep_kernel(const bf16* __restrict__ x, const bf16* __restrict__ wqkv) {
  pdl_launch();
  if (blockIdx.x == 0 && threadIdx.x > 0 && threadIdx.x < 8) g_started[threadIdx.x] = 0;
  const int lane = threadIdx.x & 31;
  const int item = ((int)blockIdx.x - PREP_QKV / 4) * 4 + (threadIdx.x >> 5);
  if (item >= 0) {
    const int row = item * 4 + (lane >> 3), q = lane & 7;
    const uint4* src = reinterpret_cast<const uint4*>(x + (size_t)row * DM) + q;
    uint4* dst = reinterpret_cast<uint4*>(g_x[0]) + (size_t)(row >> 7) * (80 * 128) + q * 128 + (row & 127);
    float s = 0.f, ss = 0.f;
    uint4 v[10];
#pragma unroll
    for (int i = 0; i < 10; i++) v[i] = ld_stream(src + i * 8, policy_stream());
#pragma unroll
    for (int i = 0; i < 10; i++) {
      dst[i * 8 * 128] = v[i];
      const uint32_t u[4] = {v[i].x, v[i].y, v[i].z, v[i].w};
#pragma unroll
      for (int j = 0; j < 4; j++) { float lo = bflo(u[j]), hi = bfhi(u[j]); s += lo + hi; ss = fmaf(lo, lo, fmaf(hi, hi, ss)); }
    }
#pragma unroll
    for (int m = 1; m < 8; m <<= 1) { s += __shfl_xor_sync(0xffffffffu, s, m); ss += __shfl_xor_sync(0xffffffffu, ss, m); }
    g_stats[row * 8 + q] = q == 0 ? make_float2(s, ss) : make_float2(0.f, 0.f);
  } else {
    __shared__ __align__(16) u8 sm[32 * 496];
    retile_wqkv(wqkv, blockIdx.x, sm);
  }
}

constexpr int GEMM_THREADS = 544;

template <int N, int NA> __device__ __forceinline__ void mma_ss(float (&d)[NA], uint64_t da, uint64_t db) {
  if constexpr (N == 120) wgmma_ss_n120<1>(d, da, db);
  if constexpr (N == 80) wgmma_ss_n80<1>(d, da, db);
  if constexpr (N == 96) wgmma_ss_n96<1>(d, da, db);
}

constexpr int RA_A = 10 * 16384, RA_RING = 60, RA_SMEM = RA_A + RA_RING * 1024;
constexpr int RA_PRE = 1;
constexpr int RA_NBAR = 51;
template <int G0, int G1> struct RingPlan {
  int off[20], dep[20];
  constexpr RingPlan() : off(), dep() {
    const int S0 = RA_RING / G0, S1 = RA_RING / G1;
    for (int i = 0; i < 10; i++) { off[i] = 160 + (i % S0) * G0; dep[i] = i < S0 ? -1 : i - S0; }
    const int st = (off[9] - 160 + G0 + G1 - 1) / G1;
    for (int k = 0; k < S1 && k < 10; k++) {
      const int o = 160 + ((st + k) % S1) * G1;
      off[10 + k] = o; dep[10 + k] = dep[9 + k];
      for (int j = 0; j < 10; j++) if (off[j] < o + G1 && o < off[j] + G0 && j > dep[10 + k]) dep[10 + k] = j;
    }
    for (int i = 10 + S1, k = 0; i < 20; i += 2, k++) {
      off[i] = off[10 + k]; dep[i] = 10 + k;
      if (i + 1 < 20) { off[i + 1] = 16 * k; dep[i + 1] = 10 + k; }
    }
  }
  __host__ __device__ constexpr uint64_t pack(int i0, int n) const { uint64_t v = 0; for (int i = 0; i < n; i++) v |= (uint64_t)off[i0 + i] << (8 * i); return v; }
};
template <int G0, int G1>
__device__ __forceinline__ void ra_producer(const u8* ga, const u8* gb, uint32_t sbase, uint32_t bar0, bool b_early) {
  constexpr RingPlan<G0, G1> P;
  const uint32_t afull = bar0, bfull = bar0 + 80, bfree = bar0 + 240;
  if (b_early) {
#pragma unroll
    for (int i = 0; i < RA_PRE; i++) bulk_g2s(sbase + P.off[i] * 1024, gb + i * G0 * 1024, G0 * 1024, bfull + 8 * i);
  }
  pdl_wait();
#pragma unroll
  for (int i = 0; i < 20; i++) {
    const int bytes = (i < 10 ? G0 : G1) * 1024;
    if (i < 10) bulk_g2s(sbase + i * 16384, ga + i * 16384, 16384, afull + 8 * i);
    if (i >= RA_PRE || !b_early) {
      if (P.dep[i] >= 0 && P.dep[i] != P.dep[i - 1]) mbar_wait(bfree + 8 * P.dep[i], 0);
      bulk_g2s(sbase + P.off[i] * 1024, gb, bytes, bfull + 8 * i);
    }
    gb += bytes;
  }
}
template <int G0, int G1, int SUB, int NA>
__device__ __forceinline__ void ra_mainloop(float (&acc)[NA], uint32_t sbase, int wi, uint32_t bar0, int lane) {
  constexpr RingPlan<G0, G1> P;
  constexpr int NG = SUB == 0 ? G0 : G1;
  const uint32_t afull = bar0, bfull = bar0 + 80 + SUB * 80, bfree = bar0 + 240 + SUB * 80;
#pragma unroll
  for (int i = 0; i < NG * 4; i++) acc[i] = 0.f;
  fence_regs(acc);
  uint64_t da = mkdesc(sbase + wi * 1024, 2048, 128);
  const uint64_t db0 = mkdesc(sbase, NG * 128, 128);
  constexpr uint64_t TAB0 = P.pack(SUB * 10, 8), TAB1 = P.pack(SUB * 10 + 8, 2);
  uint64_t tab = TAB0;
  if (SUB == 1) {
#pragma unroll 1
    for (int kb = 0; kb < 10; kb++) mbar_wait(afull + 8 * kb, 0);
  }
#pragma unroll 1
  for (int kb = 0; kb < 10; kb++) {
    if (SUB == 0) mbar_wait(afull + 8 * kb, 0);
    mbar_wait(bfull + 8 * kb, 0);
    const uint64_t db = db0 + (uint64_t)(((uint32_t)tab & 255u) * 64);
    WG_FENCE;
#pragma unroll
    for (int k = 0; k < 4; k++) mma_ss<NG * 8>(acc, da + (uint64_t)(k * 256), db + (uint64_t)(k * NG * 16));
    WG_COMMIT;
    WG_WAIT(1);
    if (kb > 0 && lane == 0) mbar_arrive(bfree + 8 * (kb - 1));
    da += 1024;
    tab = kb == 7 ? TAB1 : tab >> 8;
  }
  WG_WAIT(0);
  if (SUB == 0 && lane == 0) mbar_arrive(bfree + 72);
  fence_regs(acc);
}
template <int G0, int G1>
__device__ __forceinline__ void ra_init(uint32_t bar0, int warp, int lane) {
  if (lane == 0) {
    for (int i = warp; i < RA_NBAR; i += GEMM_THREADS / 32) {
      mbar_init(bar0 + 8 * i, i < 30 ? 1 : (i < 50 ? 8 : 256));
      if (i < 30) mbar_expect_tx(bar0 + 8 * i, i < 10 ? 16384 : (i < 20 ? G0 : G1) * 1024);
    }
    asm volatile("fence.mbarrier_init.release.cluster;" ::: "memory");
  }
  __syncthreads();
}

template <bool DOUBLE>
__device__ __forceinline__ float2 row_stats(const float4 (&p)[4]) {
  float s = (p[0].x + p[0].z) + (p[1].x + p[1].z) + (p[2].x + p[2].z) + (p[3].x + p[3].z);
  float ss = (p[0].y + p[0].w) + (p[1].y + p[1].w) + (p[2].y + p[2].w) + (p[3].y + p[3].w);
  float mean = s * (1.0f / DM);
  float var = fmaxf(ss * (1.0f / DM) - mean * mean, 0.f);
  float r = rsqrtf(var + LN_EPS);
  if (DOUBLE) r *= rsqrtf(var * r * r + LN_EPS);
  return make_float2(r, -mean * r);
}

constexpr uint32_t POLY_MASK = 0xD6D6u;
constexpr int HEAD_BYTES = SEQ * 48;
constexpr float QSCALE = 0.22360679774997896f * 1.4426950408889634f;

template <int NP, int NA>
__device__ __forceinline__ void qkv_epilogue(float (&acc)[NA], int P0, int rb, int cb, int tg, int lane, const float2* s_row, const float* s_cs) {
  const int g = lane >> 2, t = lane & 3;
  const float2 r0 = s_row[tg * 8 + g], r1 = s_row[tg * 8 + g + 8];
  u8* base = (u8*)g_qkv + (size_t)(cb * 12 + 2 * P0) * HEAD_BYTES + (rb * 16 + tg) * 384 + g * 16;
#pragma unroll
  for (int pp = 0; pp < NP; pp++) {
    const int slot = cb * 12 + 2 * (P0 + pp);
    const bool isk = slot >= 32 && slot < 64;
    const float m = slot < 32 ? QSCALE : 1.0f;
    const float a0 = r0.x * m, b0 = r0.y * m, a1 = r1.x * m, b1 = r1.y * m;
    u8* pa = base + (2 * pp) * HEAD_BYTES + 4 * t;
    float e[5][2];
#pragma unroll
    for (int j = 0; j < 5; j++) {
      const int i = 5 * pp + j;
      const float2 cs = *reinterpret_cast<const float2*>(&s_cs[P0 * 40 + 8 * i + 2 * t]);
      const float v0 = fmaf(acc[4 * i], a0, b0 * cs.x), v1 = fmaf(acc[4 * i + 1], a0, b0 * cs.y);
      const float v2 = fmaf(acc[4 * i + 2], a1, b1 * cs.x), v3 = fmaf(acc[4 * i + 3], a1, b1 * cs.y);
      const uint32_t p0 = pack2(v0, v1), p1 = pack2(v2, v3);
      e[j][0] = fmaf(v0, v0, v1 * v1); e[j][1] = fmaf(v2, v2, v3 * v3);
      if (j < 4) {
        *reinterpret_cast<uint32_t*>(pa + (j >> 1) * HEAD_BYTES + (j & 1) * 128) = p0;
        *reinterpret_cast<uint32_t*>(pa + (j >> 1) * HEAD_BYTES + (j & 1) * 128 + 384) = p1;
      } else {
        const uint32_t plain = (slot >= 32 && !(t & 1)) ? 0x00003F80u : 0u;
        const uint32_t poly = (t & 1) ? 0x3B2CBFCDu : 0x43C03F80u;
        const uint32_t pad0 = (isk && ((POLY_MASK >> tg) & 1)) ? poly : plain, pad1 = (isk && ((POLY_MASK >> (tg + 1)) & 1)) ? poly : plain;
        u8* pb = base + (2 * pp + 1) * HEAD_BYTES + 4 * (t ^ 2);
        *reinterpret_cast<uint32_t*>(pa + 256) = t < 2 ? p0 : pad0;
        *reinterpret_cast<uint32_t*>(pa + 256 + 384) = t < 2 ? p1 : pad1;
        *reinterpret_cast<uint32_t*>(pb + 256) = t < 2 ? pad0 : p0;
        *reinterpret_cast<uint32_t*>(pb + 256 + 384) = t < 2 ? pad1 : p1;
      }
    }
    if (slot < 64) {
      float na0 = e[0][0] + e[1][0] + (t < 2 ? e[4][0] : 0.f), na1 = e[0][1] + e[1][1] + (t < 2 ? e[4][1] : 0.f);
      float nb0 = e[2][0] + e[3][0] + (t < 2 ? 0.f : e[4][0]), nb1 = e[2][1] + e[3][1] + (t < 2 ? 0.f : e[4][1]);
      na0 += __shfl_xor_sync(0xffffffffu, na0, 1); na1 += __shfl_xor_sync(0xffffffffu, na1, 1);
      nb0 += __shfl_xor_sync(0xffffffffu, nb0, 1); nb1 += __shfl_xor_sync(0xffffffffu, nb1, 1);
      na0 += __shfl_xor_sync(0xffffffffu, na0, 2); na1 += __shfl_xor_sync(0xffffffffu, na1, 2);
      nb0 += __shfl_xor_sync(0xffffffffu, nb0, 2); nb1 += __shfl_xor_sync(0xffffffffu, nb1, 2);
      const uint32_t ma = __reduce_max_sync(0xffffffffu, max(__float_as_uint(na0) & 0x7FFFFFFFu, __float_as_uint(na1) & 0x7FFFFFFFu));
      const uint32_t mb = __reduce_max_sync(0xffffffffu, max(__float_as_uint(nb0) & 0x7FFFFFFFu, __float_as_uint(nb1) & 0x7FFFFFFFu));
      if (lane < 2) g_nmax[(slot + lane) * 128 + rb * 8 + (tg >> 1)] = __uint_as_float(lane == 0 ? ma : mb);
    }
  }
}
__global__ void __launch_bounds__(GEMM_THREADS, 1) qkv_kernel(int xi, int b_early, int slot, const __grid_constant__ TileMap tm) {
  extern __shared__ __align__(1024) u8 smem[];
  __shared__ __align__(8) uint64_t bars[RA_NBAR];
  __shared__ __align__(16) float2 s_row[128];
  __shared__ __align__(16) float s_cs[240];
  const int tid = threadIdx.x, warp = __shfl_sync(0xffffffffu, tid >> 5, 0), lane = tid & 31;
  const int tile = tile_enter(tm, slot);
  if (tile == 255) { pdl_launch(); if (tid == 0) tile_leave(tm, slot); return; }
  const int rb = tile & 15, cb = tile >> 4;
  const uint32_t sbase = smem_u32(smem), bar0 = smem_u32(&bars[0]), sbar = bar0 + 400;
  ra_init<QG0, QG1>(bar0, warp, lane);
  if (warp >= 16) {
    if (tid == 512) ra_producer<QG0, QG1>((const u8*)g_x[xi] + (size_t)rb * (80 * 2048), (const u8*)g_wqkv + (size_t)cb * (80 * 30 * 128), sbase, bar0, b_early);
    if (tid == 512) tile_leave(tm, slot);
    return;
  }
  pdl_wait();
  pdl_launch();
  const int wi = (warp >> 2) & 1, tg = wi * 8 + (warp & 3) * 2;
  if (warp < 8) {
    float acc[QG0 * 4];
    ra_mainloop<QG0, QG1, 0>(acc, sbase, wi, bar0, lane);
    mbar_wait(sbar, 0);
    qkv_epilogue<QG0 / 5>(acc, 0, rb, cb, tg, lane, s_row, s_cs);
  } else {
    float acc[QG1 * 4];
    const int u = tid - 256;
    float4 pre[4];
    float cp[20];
    if (u < 128) {
#pragma unroll
      for (int k = 0; k < 4; k++) pre[k] = ldg<float4>(g_stats + (rb * 128 + u) * 8 + 2 * k);
    }
    if (u < 240) {
#pragma unroll
      for (int k = 0; k < 20; k++) cp[k] = g_cs_qkv[k * NQKV + cb * 240 + u];
    }
    if (u < 128) s_row[u] = row_stats<false>(pre);
    if (u < 240) {
      float c = 0.f;
#pragma unroll
      for (int k = 0; k < 20; k++) c += cp[k];
      s_cs[u] = c;
    }
    mbar_arrive(sbar);
    ra_mainloop<QG0, QG1, 1>(acc, sbase, wi, bar0, lane);
    mbar_wait(sbar, 0);
    qkv_epilogue<QG1 / 5>(acc, QG0 / 5, rb, cb, tg, lane, s_row, s_cs);
  }
}

__device__ __forceinline__ float gelu(float hx) {
  const float y = hx * fmaf(hx * hx, 8.0f * 0.7978845608028654f * 0.044715f, 2.0f * 0.7978845608028654f);
  return fmaf(hx, tanh_fast(y), hx);
}
template <int NB, int NA>
__device__ __forceinline__ void w1_epilogue(float (&acc)[NA], const float2* s_cb, float2 r0, float2 r1, u8* base) {
#pragma unroll
  for (int i = 0; i < NB; i++) {
    const float4 cb = *reinterpret_cast<const float4*>(&s_cb[8 * i]);
    const float v0 = fmaf(acc[4 * i], r0.x, fmaf(r0.y, cb.x, cb.y)), v1 = fmaf(acc[4 * i + 1], r0.x, fmaf(r0.y, cb.z, cb.w));
    const float v2 = fmaf(acc[4 * i + 2], r1.x, fmaf(r1.y, cb.x, cb.y)), v3 = fmaf(acc[4 * i + 3], r1.x, fmaf(r1.y, cb.z, cb.w));
    *reinterpret_cast<uint32_t*>(base + i * 2048) = pack2(gelu(v0), gelu(v1));
    *reinterpret_cast<uint32_t*>(base + i * 2048 + 128) = pack2(gelu(v2), gelu(v3));
  }
}
__global__ void __launch_bounds__(GEMM_THREADS, 1) w1_kernel(int xi, const bf16* __restrict__ b1, int slot, const __grid_constant__ TileMap tm) {
  extern __shared__ __align__(1024) u8 smem[];
  __shared__ __align__(8) uint64_t bars[RA_NBAR];
  __shared__ __align__(16) float2 s_row[128];
  __shared__ __align__(16) float2 s_cb[216];
  const int tid = threadIdx.x, warp = __shfl_sync(0xffffffffu, tid >> 5, 0), lane = tid & 31;
  const int tile = tile_enter(tm, slot);
  if (tile == 255) { pdl_launch(); if (tid == 0) tile_leave(tm, slot); return; }
  const int rb = tile & 15, cb = tile >> 4;
  const uint32_t sbase = smem_u32(smem), bar0 = smem_u32(&bars[0]), sbar = bar0 + 400;
  ra_init<WG0, WG1>(bar0, warp, lane);
  if (warp >= 16) {
    if (tid == 512) ra_producer<WG0, WG1>((const u8*)g_x[xi] + (size_t)rb * (80 * 2048), (const u8*)g_w1 + (size_t)cb * (80 * 27 * 128), sbase, bar0, true);
    if (tid == 512) tile_leave(tm, slot);
    return;
  }
  const int u = tid - 256;
  if (u >= 0 && u < 216) {
    const int n = cb * 216 + u;
    float s = 0.f;
#pragma unroll
    for (int k = 0; k < 10; k++) s += g_cs_w1[k * FF + n];
    s_cb[u] = make_float2(s, 0.5f * __bfloat162float(b1[n]));
  }
  pdl_wait();
  pdl_launch();
  const int wi = (warp >> 2) & 1, t = lane & 3, lr = wi * 64 + (warp & 3) * 16 + (lane >> 2);
  u8* base = (u8*)g_h + (size_t)rb * (216 * 2048) + (size_t)(cb * 27) * 2048 + lr * 16 + t * 4;
  if (warp < 8) {
    float acc[WG0 * 4];
    ra_mainloop<WG0, WG1, 0>(acc, sbase, wi, bar0, lane);
    mbar_wait(sbar, 0);
    w1_epilogue<WG0>(acc, s_cb + 2 * t, s_row[lr], s_row[lr + 8], base);
  } else {
    float acc[WG1 * 4];
    if (u < 128) {
      float4 pre[4];
#pragma unroll
      for (int k = 0; k < 4; k++) pre[k] = ldg<float4>(g_stats + (rb * 128 + u) * 8 + 2 * k);
      const float2 r = row_stats<true>(pre);
      s_row[u] = make_float2(0.5f * r.x, 0.5f * r.y);
    }
    mbar_arrive(sbar);
    ra_mainloop<WG0, WG1, 1>(acc, sbase, wi, bar0, lane);
    mbar_wait(sbar, 0);
    w1_epilogue<WG1>(acc, s_cb + WG0 * 8 + 2 * t, s_row[lr], s_row[lr + 8], base + WG0 * 2048);
  }
}

constexpr int WO_ST = 8, WO_STB = 16384 + 10240, WO_SMEM = WO_ST * WO_STB, WO_THREADS = 288;
__global__ void __launch_bounds__(WO_THREADS, 1) wo_kernel(int slot, const __grid_constant__ TileMap tm) {
  extern __shared__ __align__(1024) u8 smem[];
  __shared__ __align__(8) uint64_t bars[12];
  const int tid = threadIdx.x, warp = __shfl_sync(0xffffffffu, tid >> 5, 0), lane = tid & 31;
  const int tile = tile_enter(tm, slot);
  if (tile == 255) { pdl_launch(); if (tid == 0) tile_leave(tm, slot); return; }
  const int rb = tile & 15, cb = tile >> 4;
  const uint32_t sbase = smem_u32(smem), full0 = smem_u32(&bars[0]), free0 = full0 + 80;
  if (lane == 0) {
    for (int i = warp; i < 12; i += 9) {
      mbar_init(full0 + 8 * i, i < 10 ? 1 : 8);
      if (i < 10) mbar_expect_tx(full0 + 8 * i, WO_STB);
    }
    asm volatile("fence.mbarrier_init.release.cluster;" ::: "memory");
  }
  __syncthreads();
  if (warp == 8) {
    if (lane == 0) {
      const u8* ga = (const u8*)g_o + (size_t)rb * (80 * 2048);
      const u8* gb = (const u8*)g_wo + (size_t)cb * (80 * 1280);
      pdl_wait();
#pragma unroll
      for (int kb = 0; kb < 10; kb++) {
        if (kb >= WO_ST) mbar_wait(free0 + 8 * (kb - WO_ST), 0);
        bulk_g2s_ef(sbase + (kb % WO_ST) * WO_STB, ga + kb * 16384, 16384, full0 + 8 * kb);
        bulk_g2s(sbase + (kb % WO_ST) * WO_STB + 16384, gb + kb * 10240, 10240, full0 + 8 * kb);
      }
      tile_leave(tm, slot);
    }
    return;
  }
  const int t = lane & 3, lr = warp * 16 + (lane >> 2);
  const size_t xoff = (size_t)rb * (80 * 2048) + (size_t)cb * 10 * 2048 + lr * 16 + t * 4;
  uint32_t res[20];
#pragma unroll
  for (int i = 0; i < 20; i++) res[i] = ldg<uint32_t>((const u8*)g_x[0] + xoff + (i >> 1) * 2048 + (i & 1) * 128);
  pdl_wait();
  pdl_launch();
  float acc[40];
#pragma unroll
  for (int i = 0; i < 40; i++) acc[i] = 0.f;
  fence_regs(acc);
  const uint64_t da0 = mkdesc(sbase + (warp >> 2) * 1024, 2048, 128), db0 = mkdesc(sbase + 16384, 1280, 128);
#pragma unroll 1
  for (int kb = 0; kb < 10; kb++) {
    mbar_wait(full0 + 8 * kb, 0);
    const uint64_t o = (uint64_t)((kb < WO_ST ? kb : kb - WO_ST) * (WO_STB >> 4));
    WG_FENCE;
#pragma unroll
    for (int k = 0; k < 4; k++) mma_ss<80>(acc, da0 + o + (uint64_t)(k * 256), db0 + o + (uint64_t)(k * 160));
    WG_COMMIT;
    if (kb <= 10 - WO_ST) {
      WG_WAIT(1);
      if (kb > 0 && lane == 0) mbar_arrive(free0 + 8 * (kb - 1));
    }
  }
  WG_WAIT(0);
  fence_regs(acc);
  float s0 = 0.f, ss0 = 0.f, s1 = 0.f, ss1 = 0.f;
  u8* xo = (u8*)g_x[1] + xoff;
#pragma unroll
  for (int i = 0; i < 10; i++) {
    const uint32_t p0 = pack2(acc[4 * i] + bflo(res[2 * i]), acc[4 * i + 1] + bfhi(res[2 * i]));
    const uint32_t p1 = pack2(acc[4 * i + 2] + bflo(res[2 * i + 1]), acc[4 * i + 3] + bfhi(res[2 * i + 1]));
    *reinterpret_cast<uint32_t*>(xo + i * 2048) = p0;
    *reinterpret_cast<uint32_t*>(xo + i * 2048 + 128) = p1;
    const float v0 = bflo(p0), v1 = bfhi(p0), v2 = bflo(p1), v3 = bfhi(p1);
    s0 += v0 + v1; ss0 = fmaf(v0, v0, fmaf(v1, v1, ss0));
    s1 += v2 + v3; ss1 = fmaf(v2, v2, fmaf(v3, v3, ss1));
  }
#pragma unroll
  for (int m = 1; m < 4; m <<= 1) {
    s0 += __shfl_xor_sync(0xffffffffu, s0, m); ss0 += __shfl_xor_sync(0xffffffffu, ss0, m);
    s1 += __shfl_xor_sync(0xffffffffu, s1, m); ss1 += __shfl_xor_sync(0xffffffffu, ss1, m);
  }
  if (t < 2) g_stats[(rb * 128 + lr + 8 * t) * 8 + cb] = t == 0 ? make_float2(s0, ss0) : make_float2(s1, ss1);
}

constexpr int W2_ST = 6, W2_NIT = 18, W2_AB = 3 * 4096, W2_BB = 3 * 5120, W2_STB = W2_AB + W2_BB, W2_PRE = 3;
constexpr int W2_RING = W2_ST * W2_STB, W2_SMEM = W2_RING + 20480 + 16 * 1408;
__global__ void __cluster_dims__(2, 1, 1) __launch_bounds__(GEMM_THREADS, 1) w2_kernel(const bf16* __restrict__ bias, bf16* __restrict__ out) {
  extern __shared__ __align__(1024) u8 smem[];
  __shared__ __align__(8) uint64_t bars[2 * W2_ST + 1];
  const int tid = threadIdx.x, warp = __shfl_sync(0xffffffffu, tid >> 5, 0), lane = tid & 31;
  const int kh = blockIdx.x & 1, rb = (blockIdx.x >> 1) & 15, cb = blockIdx.x >> 5;
  const uint32_t sbase = smem_u32(smem), full0 = smem_u32(&bars[0]), empty0 = full0 + 8 * W2_ST, xbar = full0 + 16 * W2_ST;
  if (lane == 0 && warp <= 2 * W2_ST) {
    mbar_init(full0 + 8 * warp, (warp < W2_ST || warp == 2 * W2_ST) ? 1 : 16);
    if (warp < W2_ST) mbar_expect_tx(full0 + 8 * warp, W2_STB);
    if (warp == 2 * W2_ST) mbar_expect_tx(xbar, 20480);
    asm volatile("fence.mbarrier_init.release.cluster;" ::: "memory");
  }
  __syncthreads();
  if (warp == 16) {
    if (lane == 0) {
      const u8* ga = (const u8*)g_h + (size_t)(rb * 216 + kh * 108) * 2048;
      const u8* gb = (const u8*)g_w2 + (size_t)(cb * 216 + kh * 108) * 2560;
#pragma unroll
      for (int s = 0; s < W2_PRE; s++) bulk_g2s(sbase + s * W2_STB + W2_AB, gb + s * W2_BB, W2_BB, full0 + 8 * s);
      pdl_wait();
#pragma unroll
      for (int s = 0; s < W2_ST; s++) {
        bulk_g2s(sbase + s * W2_STB, ga + s * W2_AB, W2_AB, full0 + 8 * s);
        if (s >= W2_PRE) bulk_g2s(sbase + s * W2_STB + W2_AB, gb + s * W2_BB, W2_BB, full0 + 8 * s);
      }
      int s = 0; uint32_t ph = 0;
#pragma unroll 1
      for (int it = W2_ST; it < W2_NIT; it++) {
        mbar_wait(empty0 + 8 * s, ph);
        mbar_expect_tx(full0 + 8 * s, W2_STB);
        bulk_g2s(sbase + s * W2_STB, ga + it * W2_AB, W2_AB, full0 + 8 * s);
        bulk_g2s(sbase + s * W2_STB + W2_AB, gb + it * W2_BB, W2_BB, full0 + 8 * s);
        if (++s == W2_ST) { s = 0; ph ^= 1; }
      }
    }
    return;
  }
  asm volatile("barrier.cluster.arrive.relaxed.aligned;" ::: "memory");
  const int wg = warp >> 2, wi = wg & 1, wj = wg >> 1, g = lane >> 2, t = lane & 3;
  const bool fin = wi == kh;
  const int lr = wi * 64 + (warp & 3) * 16 + g, c80 = cb * 2 + wj;
  const size_t xoff = (size_t)rb * (80 * 2048) + (size_t)c80 * 10 * 2048 + lr * 16 + t * 4;
  uint32_t res[20], bs[10];
  if (fin) {
#pragma unroll
    for (int i = 0; i < 20; i++) res[i] = ldg<uint32_t>((const u8*)g_x[1] + xoff + (i >> 1) * 2048 + (i & 1) * 128);
#pragma unroll
    for (int i = 0; i < 10; i++) bs[i] = __ldg(reinterpret_cast<const uint32_t*>(bias + c80 * 80 + 8 * i + 2 * t));
  }
  pdl_wait();
  pdl_launch();
  float acc[40];
#pragma unroll
  for (int i = 0; i < 40; i++) acc[i] = 0.f;
  fence_regs(acc);
  {
    const uint64_t da0 = mkdesc(sbase + wi * 1024, 2048, 128), db0 = mkdesc(sbase + W2_AB + wj * 1280, 2560, 128);
    int s = 0, sp = 0; uint32_t ph = 0;
#pragma unroll 1
    for (int it = 0; it < W2_NIT; it++) {
      mbar_wait(full0 + 8 * s, ph);
      const uint64_t o = (uint64_t)(s * (W2_STB >> 4));
      WG_FENCE;
#pragma unroll
      for (int k = 0; k < 3; k++) mma_ss<80>(acc, da0 + o + (uint64_t)(k * 256), db0 + o + (uint64_t)(k * 320));
      WG_COMMIT;
      WG_WAIT(1);
      if (it > 0 && lane == 0) mbar_arrive(empty0 + 8 * sp);
      sp = s;
      if (++s == W2_ST) { s = 0; ph ^= 1; }
    }
    WG_WAIT(0);
    fence_regs(acc);
  }
  asm volatile("barrier.cluster.wait.aligned;" ::: "memory");
  const uint32_t xslot = W2_RING + wj * 10240 + (tid & 127) * 16;
  if (!fin) {
    uint32_t peer, peer_bar;
    asm volatile("mapa.shared::cluster.u32 %0, %1, %2;" : "=r"(peer) : "r"(sbase + xslot), "r"(kh ^ 1));
    asm volatile("mapa.shared::cluster.u32 %0, %1, %2;" : "=r"(peer_bar) : "r"(xbar), "r"(kh ^ 1));
#pragma unroll
    for (int i = 0; i < 5; i++)
      asm volatile("st.async.weak.shared::cluster.mbarrier::complete_tx::bytes.v4.b32 [%0], {%1,%2,%3,%4}, [%5];" ::"r"(peer + i * 2048), "r"(pack2(acc[8 * i], acc[8 * i + 1])),
                   "r"(pack2(acc[8 * i + 2], acc[8 * i + 3])), "r"(pack2(acc[8 * i + 4], acc[8 * i + 5])), "r"(pack2(acc[8 * i + 6], acc[8 * i + 7])), "r"(peer_bar) : "memory");
    return;
  }
  mbar_wait(xbar, 0);
  float s0 = 0.f, ss0 = 0.f, s1 = 0.f, ss1 = 0.f;
  u8* xo = (u8*)g_x[0] + xoff;
  u8* stg = smem + W2_RING + 20480 + (wj * 4 + (warp & 3)) * 2816;
#pragma unroll
  for (int j = 0; j < 5; j++) {
    const uint4 r = *reinterpret_cast<const uint4*>(smem + xslot + j * 2048);
    const uint32_t rq[4] = {r.x, r.y, r.z, r.w};
#pragma unroll
    for (int h = 0; h < 2; h++) {
      const int i = 2 * j + h;
      const uint32_t p0 = pack2(acc[4 * i] + bflo(rq[2 * h]) + bflo(res[2 * i]) + bflo(bs[i]), acc[4 * i + 1] + bfhi(rq[2 * h]) + bfhi(res[2 * i]) + bfhi(bs[i]));
      const uint32_t p1 = pack2(acc[4 * i + 2] + bflo(rq[2 * h + 1]) + bflo(res[2 * i + 1]) + bflo(bs[i]), acc[4 * i + 3] + bfhi(rq[2 * h + 1]) + bfhi(res[2 * i + 1]) + bfhi(bs[i]));
      if (out != nullptr) {
        *reinterpret_cast<uint32_t*>(stg + g * 176 + t * 4 + 16 * i) = p0;
        *reinterpret_cast<uint32_t*>(stg + (g + 8) * 176 + t * 4 + 16 * i) = p1;
      } else {
        *reinterpret_cast<uint32_t*>(xo + i * 2048) = p0;
        *reinterpret_cast<uint32_t*>(xo + i * 2048 + 128) = p1;
        const float v0 = bflo(p0), v1 = bfhi(p0), v2 = bflo(p1), v3 = bfhi(p1);
        s0 += v0 + v1; ss0 = fmaf(v0, v0, fmaf(v1, v1, ss0));
        s1 += v2 + v3; ss1 = fmaf(v2, v2, fmaf(v3, v3, ss1));
      }
    }
  }
  if (out == nullptr) {
#pragma unroll
    for (int m = 1; m < 4; m <<= 1) {
      s0 += __shfl_xor_sync(0xffffffffu, s0, m); ss0 += __shfl_xor_sync(0xffffffffu, ss0, m);
      s1 += __shfl_xor_sync(0xffffffffu, s1, m); ss1 += __shfl_xor_sync(0xffffffffu, ss1, m);
    }
    if (t < 2) g_stats[(rb * 128 + lr + 8 * t) * 8 + c80] = t == 0 ? make_float2(s0, ss0) : make_float2(s1, ss1);
  } else {
    __syncwarp();
    u8* po = (u8*)(out + (size_t)(rb * 128 + lr - g) * DM + c80 * 80);
#pragma unroll
    for (int i = 0; i < 5; i++) {
      const int c = lane + 32 * i, r = c / 10, q = c - r * 10;
      *reinterpret_cast<uint4*>(po + r * (DM * 2) + q * 16) = *reinterpret_cast<const uint4*>(stg + r * 176 + q * 16);
    }
  }
}

constexpr int ATT_EARLY = 2;
constexpr int CH_BYTES = 6144, ATT_SMEM = 2 * HEAD_BYTES + 16384;
constexpr float M_THRESH = 47.0f;

__device__ __forceinline__ uint32_t exp2_pk(float t0, float t1, uint32_t C) {
  const uint32_t S = __byte_perm(__float_as_uint(t0), __float_as_uint(t1), 0x6521);
  uint32_t z, e, r;
  asm("lop3.b32 %0, %1, 0x807F807F, %2, 0xE2;" : "=r"(z) : "r"(S), "r"(C));
  asm("lop3.b32 %0, %1, 0x7F807F80, %2, 0xE2;" : "=r"(e) : "r"(S), "r"(C));
  asm("fma.rn.bf16x2 %0, %1, %2, %3;" : "=r"(r) : "r"(S), "r"(z), "r"(e));
  return r;
}

struct SideMaps { CUtensorMap w1a, w1b, w2, wo; };
constexpr int SJ_W1A = 5 * WG0 * 128, SJ_W1B = 5 * WG1 * 128, SJ_WO = 5 * 10 * 128, SJ_W2 = 8 * 20 * 128;
__global__ void __launch_bounds__(512, 1) attn_kernel(uint32_t cbits, int side, const bf16* __restrict__ w1, const __grid_constant__ SideMaps maps) {
  extern __shared__ __align__(1024) u8 smem[];
  __shared__ __align__(8) uint64_t full[17];
  const int tid = threadIdx.x, warp = __shfl_sync(0xffffffffu, tid >> 5, 0), lane = tid & 31;
  if (blockIdx.x >= 128) {
    pdl_launch();
    if (blockIdx.x == 128 && tid == 0) { pdl_wait(); g_started[0] = 0; }
    const int u = (blockIdx.x - 128) * 512 + tid;
    for (int w = u; w < 2160; w += 2048) {
      const int kb = w / 216, g = w - kb * 216;
      const uint4* src = reinterpret_cast<const uint4*>(w1 + (size_t)kb * 64 * FF + g * 8);
      float s[8];
#pragma unroll
      for (int i = 0; i < 8; i++) s[i] = 0.f;
#pragma unroll 16
      for (int r = 0; r < 64; r++) {
        const uint4 v = ld_stream(src + r * (FF / 8), policy_stream());
        s[0] += bflo(v.x); s[1] += bfhi(v.x); s[2] += bflo(v.y); s[3] += bfhi(v.y);
        s[4] += bflo(v.z); s[5] += bfhi(v.z); s[6] += bflo(v.w); s[7] += bfhi(v.w);
      }
      float4* d = reinterpret_cast<float4*>(g_cs_w1 + kb * FF + g * 8);
      d[0] = make_float4(s[0], s[1], s[2], s[3]);
      d[1] = make_float4(s[4], s[5], s[6], s[7]);
    }
    return;
  }
  const int head = blockIdx.x >> 2, qb = blockIdx.x & 3;
  const uint32_t sK = smem_u32(smem), sV = sK + HEAD_BYTES;
  if (lane == 0) {
    mbar_init(smem_u32(&full[warp]), 1);
    if (warp == 0) mbar_init(smem_u32(&full[16]), 1);
    asm volatile("fence.mbarrier_init.release.cluster;" ::: "memory");
  }
  __syncthreads();
  const u8* gq = (const u8*)g_qkv;
  auto issue_chunk = [&](int c) {
    if (lane == 0) {
      const u8* gk = gq + (size_t)(32 + head) * HEAD_BYTES + c * CH_BYTES;
      const uint32_t b = smem_u32(&full[c]);
      mbar_expect_tx(b, 2 * CH_BYTES);
      bulk_g2s(sK + c * CH_BYTES, gk, CH_BYTES, b);
      bulk_g2s(sV + c * CH_BYTES, gk + (size_t)32 * HEAD_BYTES, CH_BYTES, b);
    }
    __syncwarp();
  };
  auto side_load = [&]() {
    if (lane == 0) {
      const uint32_t b = smem_u32(&full[16]), dk = sK + 12 * CH_BYTES, dv = sV + 12 * CH_BYTES;
      const int c8 = blockIdx.x & 7, o5 = (blockIdx.x >> 3) * 5;
      const bool w2 = blockIdx.x < 108;
      mbar_expect_tx(b, SJ_W1A + SJ_W1B + SJ_WO + (w2 ? SJ_W2 : 0));
      tma_4d(dk, &maps.wo, c8 * 10, o5, b);
      tma_4d(dk + SJ_WO, &maps.w1a, c8 * 27, o5, b);
      tma_4d(dk + SJ_WO + SJ_W1A, &maps.w1b, c8 * 27 + WG0, o5, b);
      if (w2) tma_4d(dv, &maps.w2, (blockIdx.x & 3) * 20, (blockIdx.x >> 2) * 8, b);
    }
    __syncwarp();
  };
  auto side_store = [&]() {
    mbar_wait(smem_u32(&full[16]), 0);
    if (lane == 0) {
      const uint32_t dk = sK + 12 * CH_BYTES, dv = sV + 12 * CH_BYTES;
      const int c8 = blockIdx.x & 7, o5 = (blockIdx.x >> 3) * 5;
      bulk_store((u8*)g_wo + (c8 * 80 + o5) * 1280, dk, SJ_WO);
      bulk_store((u8*)g_w1 + c8 * (27 * 80 * 128) + o5 * (WG0 * 128), dk + SJ_WO, SJ_W1A);
      bulk_store((u8*)g_w1 + c8 * (27 * 80 * 128) + WG0 * 80 * 128 + o5 * (WG1 * 128), dk + SJ_WO + SJ_W1A, SJ_W1B);
      if (blockIdx.x < 108) bulk_store((u8*)g_w2 + ((blockIdx.x & 3) * 216 + (blockIdx.x >> 2) * 8) * 2560, dv, SJ_W2);
      asm volatile("cp.async.bulk.commit_group;" ::: "memory");
    }
    __syncwarp();
  };
  auto late_chunks = [&]() {
    asm volatile("cp.async.bulk.wait_group.read 0;" ::: "memory");
    if (lane == 0) {
      const u8* gk = gq + (size_t)(32 + head) * HEAD_BYTES + 12 * CH_BYTES;
      const uint32_t b = smem_u32(&full[12]);
      mbar_expect_tx(b, 8 * CH_BYTES);
      bulk_g2s(sK + 12 * CH_BYTES, gk, 4 * CH_BYTES, b);
      bulk_g2s(sV + 12 * CH_BYTES, gk + (size_t)32 * HEAD_BYTES, 4 * CH_BYTES, b);
    }
    __syncwarp();
  };
  const int wg = warp >> 2, g = lane >> 2, t = lane & 3;
  const int row0 = qb * 512 + wg * 128 + (warp & 3) * 16;
  uint4* cst = reinterpret_cast<uint4*>(smem + 2 * HEAD_BYTES + 12288) + lane;
  *cst = make_uint4(cbits, 0u, 0u, 0u);
  uint32_t cb_, z0, z1;
  asm volatile("{\n.reg .b32 t;\nld.volatile.shared.v4.u32 {%0,t,%1,%2}, [%3];\n}" : "=r"(cb_), "=r"(z0), "=r"(z1) : "r"(smem_u32(cst)) : "memory");
  pdl_wait();
  pdl_launch();
  uint32_t qa[6], qc[6];
  {
    const u8* qp = gq + (size_t)head * HEAD_BYTES + (row0 >> 3) * 384 + g * 16 + t * 4;
    auto ld = [&](int off) { return ldg<uint32_t>(qp + off); };
    qa[0] = ld(0); qa[1] = ld(384); qa[2] = ld(128); qa[3] = ld(512);
    qc[0] = ld(3072); qc[1] = ld(3072 + 384); qc[2] = ld(3072 + 128); qc[3] = ld(3072 + 512);
    qa[4] = qa[5] = qc[4] = qc[5] = 0;
    if (t < 2) { qa[4] = ld(256); qa[5] = ld(640); qc[4] = ld(3072 + 256); qc[5] = ld(3072 + 640); }
  }
  const uint4 km4 = ldg<uint4>(g_nmax + (32 + head) * 128 + lane * 4);
  const uint32_t qm1 = ldg<uint32_t>(g_nmax + head * 128 + qb * 32 + wg * 8 + (lane & 7));
  if (warp < ATT_EARLY) issue_chunk(warp);
  const float km = __uint_as_float(__reduce_max_sync(0xffffffffu, max(max(km4.x, km4.y), max(km4.z, km4.w))));
  const float qm = __uint_as_float(__reduce_max_sync(0xffffffffu, qm1));
  const float mrow = sqrt_fast(km * qm * 1.03f);
  const bool okall = mrow <= M_THRESH;
  float o[12] = {};
  auto epilogue = [&](int pass) {
    const float l0 = __shfl_sync(0xffffffffu, o[8], (lane & ~3) | 2), l1 = __shfl_sync(0xffffffffu, o[10], (lane & ~3) | 2);
    const float i0 = __frcp_rn(l0), i1 = __frcp_rn(l1);
    const int r0 = row0 + pass * 64 + g;
    u8* go = (u8*)g_o + (r0 >> 7) * (80 * 2048) + (r0 & 127) * 16;
#pragma unroll
    for (int i = 0; i < 3; i++) {
      const int dcol = 8 * i + 2 * t;
      if (dcol < 20) {
        const int c = head * 20 + dcol;
        const int off = (c >> 3) * 2048 + (c & 7) * 2;
        *reinterpret_cast<uint32_t*>(go + off) = pack2(o[4 * i] * i0, o[4 * i + 1] * i0);
        *reinterpret_cast<uint32_t*>(go + off + 128) = pack2(o[4 * i + 2] * i1, o[4 * i + 3] * i1);
      }
    }
  };
  constexpr uint64_t HALF = 3072 >> 4;
  constexpr uint64_t K2 = (uint64_t)(256 >> 4) - ((uint64_t)(128 >> 4) << 16);
  if (okall) {
    if (t == 2) qa[4] = qa[5] = qc[4] = qc[5] = ((__float_as_uint(-mrow) + 0xFFFFu) >> 16) | 0x3F800000u;
    if (t == 3) qa[4] = qa[5] = qc[4] = qc[5] = 0x3F803F80u;
    uint2* qst = reinterpret_cast<uint2*>(smem + 2 * HEAD_BYTES) + tid;
    auto exp32 = [&](float (&s)[32], uint32_t (&p)[16], int hf) {
#pragma unroll
      for (int i = 0; i < 8; i++) {
        if ((POLY_MASK >> (i + 8 * hf)) & 1) { p[2 * i] = exp2_pk(s[4 * i], s[4 * i + 1], cb_); p[2 * i + 1] = exp2_pk(s[4 * i + 2], s[4 * i + 3], cb_); }
        else { p[2 * i] = pack2(ex2(s[4 * i]), ex2(s[4 * i + 1])); p[2 * i + 1] = pack2(ex2(s[4 * i + 2]), ex2(s[4 * i + 3])); }
      }
    };
    auto pv4 = [&](uint32_t (&p)[16], uint64_t dv, bool z) {
      if (z) wgmma_rs_n24_z<1>(o, p[0], p[1], p[2], p[3], dv); else wgmma_rs_n24<1>(o, p[0], p[1], p[2], p[3], dv);
#pragma unroll
      for (int k = 1; k < 4; k++) wgmma_rs_n24<1>(o, p[4 * k], p[4 * k + 1], p[4 * k + 2], p[4 * k + 3], dv + (uint64_t)(k * 768 >> 4));
    };
    auto qk = [&](float (&s)[32], uint64_t dk) {
      wgmma_rs_n64_z<0>(s, qa[0], qa[1], qa[2], qa[3], dk);
      wgmma_rs_n64<0>(s, qa[4], qa[5], z0, z1, dk + K2);
    };
    const uint64_t dk0 = mkdesc(sK, 128, 384), dv0 = mkdesc(sV, 384, 128);
    float s[32]; uint32_t pa[16], pb[16];
    mbar_wait(smem_u32(&full[0]), 0);
    WG_FENCE; qk(s, dk0); WG_COMMIT;
    qst[0] = make_uint2(qc[0], qc[1]); qst[512] = make_uint2(qc[2], qc[3]); qst[1024] = make_uint2(qc[4], qc[5]);
    if (warp >= ATT_EARLY && warp < 6) issue_chunk(warp);
#pragma unroll
    for (int pass = 0; pass < 2; pass++) {
      uint64_t dk = dk0, dv = dv0;
      if (pass == 0) { WG_WAIT(0); }
      fence_regs(s);
      exp32(s, pa, 0); WG_FENCE; qk(s, dk + HALF); WG_COMMIT; pv4(pa, dv, true); WG_COMMIT;
      if (pass == 0) mbar_wait(smem_u32(&full[1]), 0);
      WG_WAIT(1); fence_regs(s);
      exp32(s, pb, 1); WG_FENCE; qk(s, dk + 2 * HALF); WG_COMMIT; pv4(pb, dv + HALF, false); WG_COMMIT;
      WG_WAIT(1);
      dk += 2 * HALF; dv += 2 * HALF;
      if (pass == 0 && warp >= 6 && warp < 12) issue_chunk(warp);
      if (pass == 0 && warp == 12 && side) side_load();
#pragma unroll 1
      for (int seg = 0; seg < (pass == 0 ? 4 : 1); seg++) {
        int n = 14;
        if (pass == 0) {
          n = seg == 2 ? 2 : 4;
          const int c0 = seg < 3 ? 2 + 4 * seg : 12, c1 = seg < 2 ? c0 + 4 : (seg == 2 ? 12 : 13);
#pragma unroll 1
          for (int c = c0; c < c1; c++) mbar_wait(smem_u32(&full[c]), 0);
        }
        const uint32_t dend = (uint32_t)dk + n * 2 * (uint32_t)HALF;
#pragma unroll 1
        while ((uint32_t)dk != dend) {
          fence_regs(s);
          exp32(s, pa, 0); WG_FENCE; qk(s, dk + HALF); WG_COMMIT; pv4(pa, dv, false); WG_COMMIT;
          WG_WAIT(1); fence_regs(s);
          exp32(s, pb, 1); WG_FENCE; qk(s, dk + 2 * HALF); WG_COMMIT; pv4(pb, dv + HALF, false); WG_COMMIT;
          WG_WAIT(1);
          dk += 2 * HALF; dv += 2 * HALF;
        }
        if (pass == 0 && warp == 12) {
          if (seg == 0 && side) side_store();
          if (seg == 1) late_chunks();
        }
      }
      fence_regs(s);
      exp32(s, pa, 0); WG_FENCE; qk(s, dk + HALF); WG_COMMIT; pv4(pa, dv, false); WG_COMMIT;
      WG_WAIT(1); fence_regs(s);
      if (pass == 0) { const uint2 v0 = qst[0], v1 = qst[512], v2 = qst[1024]; qa[0] = v0.x; qa[1] = v0.y; qa[2] = v1.x; qa[3] = v1.y; qa[4] = v2.x; qa[5] = v2.y; }
      exp32(s, pb, 1); WG_FENCE; pv4(pb, dv + HALF, false);
      if (pass == 0) qk(s, dk0);
      WG_COMMIT;
      WG_WAIT(0);
      fence_regs(o);
      epilogue(pass);
    }
  } else {
    if (warp >= ATT_EARLY && warp < 12) issue_chunk(warp);
    if (warp == 12) { if (side) { side_load(); side_store(); } late_chunks(); }
#pragma unroll 1
    for (int pass = 0; pass < 2; pass++) {
      uint32_t q[6];
#pragma unroll
      for (int i = 0; i < 6; i++) q[i] = pass == 0 ? qa[i] : qc[i];
#pragma unroll
      for (int i = 0; i < 12; i++) o[i] = 0.f;
      float mx0 = -INFINITY, mx1 = -INFINITY;
      float s[32]; uint32_t p[16];
      uint64_t dk = mkdesc(sK, 128, 384), dv = mkdesc(sV, 384, 128);
#pragma unroll 1
      for (int j = 0; j < 32; j++) {
        if (pass == 0) mbar_wait(smem_u32(&full[min(j >> 1, 12)]), 0);
        WG_FENCE;
        wgmma_rs_n64_z<0>(s, q[0], q[1], q[2], q[3], dk);
        wgmma_rs_n64<0>(s, q[4], q[5], 0, 0, dk + K2);
        WG_COMMIT;
        WG_WAIT(0);
        fence_regs(s); fence_regs(o);
        float a0 = mx0, a1 = mx1;
#pragma unroll
        for (int i = 0; i < 8; i++) { a0 = fmaxf(a0, fmaxf(s[4 * i], s[4 * i + 1])); a1 = fmaxf(a1, fmaxf(s[4 * i + 2], s[4 * i + 3])); }
        a0 = fmaxf(a0, __shfl_xor_sync(0xffffffffu, a0, 1)); a0 = fmaxf(a0, __shfl_xor_sync(0xffffffffu, a0, 2));
        a1 = fmaxf(a1, __shfl_xor_sync(0xffffffffu, a1, 1)); a1 = fmaxf(a1, __shfl_xor_sync(0xffffffffu, a1, 2));
        const float r0 = ex2(mx0 - a0), r1 = ex2(mx1 - a1);
        mx0 = a0; mx1 = a1;
#pragma unroll
        for (int i = 0; i < 3; i++) { o[4 * i] *= r0; o[4 * i + 1] *= r0; o[4 * i + 2] *= r1; o[4 * i + 3] *= r1; }
#pragma unroll
        for (int i = 0; i < 8; i++) {
          p[2 * i] = pack2(ex2(s[4 * i] - a0), ex2(s[4 * i + 1] - a0)); p[2 * i + 1] = pack2(ex2(s[4 * i + 2] - a1), ex2(s[4 * i + 3] - a1));
        }
        fence_regs(o);
        WG_FENCE;
#pragma unroll
        for (int k = 0; k < 4; k++) wgmma_rs_n24<1>(o, p[4 * k], p[4 * k + 1], p[4 * k + 2], p[4 * k + 3], dv + (uint64_t)(k * 768 >> 4));
        WG_COMMIT;
        WG_WAIT(0);
        dk += HALF; dv += HALF;
      }
      fence_regs(o);
      epilogue(pass);
    }
  }
  if (warp == 12) asm volatile("cp.async.bulk.wait_group 0;" ::: "memory");
}

template <typename... KArgs, typename... Args>
void launch(void (*kern)(KArgs...), int grid, int block, int smem, bool pdl, Args... args) {
  cudaLaunchConfig_t cfg = {};
  cfg.gridDim = dim3(grid); cfg.blockDim = dim3(block); cfg.dynamicSmemBytes = smem; cfg.stream = cudaStreamPerThread;
  cudaLaunchAttribute at[1];
  at[0].id = cudaLaunchAttributeProgrammaticStreamSerialization;
  at[0].val.programmaticStreamSerializationAllowed = 1;
  cfg.attrs = at; cfg.numAttrs = pdl ? 1 : 0;
  cudaLaunchKernelEx(&cfg, kern, KArgs(args)...);
}

}

extern "C" void kernel_launch(void* const* d_in, const int* in_sizes, int n_in, void* d_out, int out_size) {
  (void)in_sizes; (void)n_in; (void)out_size;
  const bf16* x = (const bf16*)d_in[0];
  const bf16* wqkv = (const bf16*)d_in[1];
  const bf16* wo = (const bf16*)d_in[2];
  const bf16* w1 = (const bf16*)d_in[4];
  const bf16* b1 = (const bf16*)d_in[5];
  const bf16* w2 = (const bf16*)d_in[6];
  const bf16* b2 = (const bf16*)d_in[7];
  static bool init = false;
  static TileMap tm;
  if (!init) {
    int dev = 0, sms = 0;
    cudaGetDevice(&dev);
    cudaDeviceGetAttribute(&sms, cudaDevAttrMultiProcessorCount, dev);
    tm.use = sms == 132;
    int cnt[8] = {0};
    for (int s = 0; s < 132; s++) {
      const int tp = s >> 1, g = tp < 32 ? tp & 7 : (tp < 60 ? 1 + (tp - 32) % 7 : 0), t = cnt[g]++;
      tm.t[s] = t < 16 ? ((g & 1) * 4 + (t & 3)) * 16 + (g >> 1) * 4 + (t >> 2) : 255;
    }
  }
  const int grid = tm.use ? 132 : 128;
  static SideMaps maps;
  static const void* mapped[3];
  if (!init || mapped[0] != wo || mapped[1] != w1 || mapped[2] != w2) {
    typedef CUresult (*EncFn)(CUtensorMap*, CUtensorMapDataType, cuuint32_t, void*, const cuuint64_t*, const cuuint64_t*, const cuuint32_t*, const cuuint32_t*,
                              CUtensorMapInterleave, CUtensorMapSwizzle, CUtensorMapL2promotion, CUtensorMapFloatOOBfill);
    EncFn enc = nullptr;
    cudaDriverEntryPointQueryResult qr;
    cudaGetDriverEntryPoint("cuTensorMapEncodeTiled", (void**)&enc, cudaEnableDefault, &qr);
    auto make = [&](CUtensorMap* m, const bf16* w, int N, int K, int ng, int oct) {
      const cuuint64_t gd[4] = {8, 8, (cuuint64_t)N / 8, (cuuint64_t)K / 8};
      const cuuint64_t gs[3] = {(cuuint64_t)N * 2, 16, (cuuint64_t)N * 16};
      const cuuint32_t bd[4] = {8, 8, (cuuint32_t)ng, (cuuint32_t)oct}, es[4] = {1, 1, 1, 1};
      enc(m, CU_TENSOR_MAP_DATA_TYPE_BFLOAT16, 4, (void*)w, gd, gs, bd, es, CU_TENSOR_MAP_INTERLEAVE_NONE, CU_TENSOR_MAP_SWIZZLE_NONE,
          CU_TENSOR_MAP_L2_PROMOTION_L2_128B, CU_TENSOR_MAP_FLOAT_OOB_FILL_NONE);
    };
    make(&maps.w1a, w1, FF, DM, WG0, 5);
    make(&maps.w1b, w1, FF, DM, WG1, 5);
    make(&maps.w2, w2, DM, FF, 20, 8);
    make(&maps.wo, wo, DM, DM, 10, 5);
    mapped[0] = wo; mapped[1] = w1; mapped[2] = w2;
  }
  if (!init) {
    cudaFuncSetAttribute(qkv_kernel, cudaFuncAttributeMaxDynamicSharedMemorySize, RA_SMEM);
    cudaFuncSetAttribute(w1_kernel, cudaFuncAttributeMaxDynamicSharedMemorySize, RA_SMEM);
    cudaFuncSetAttribute(w2_kernel, cudaFuncAttributeMaxDynamicSharedMemorySize, W2_SMEM);
    cudaFuncSetAttribute(wo_kernel, cudaFuncAttributeMaxDynamicSharedMemorySize, WO_SMEM);
    cudaFuncSetAttribute(attn_kernel, cudaFuncAttributeMaxDynamicSharedMemorySize, ATT_SMEM);
    init = true;
  }
  launch(prep_kernel, (PREP_X + PREP_QKV) / 4, 128, 0, false, x, wqkv);
  for (int layer = 0; layer < 2; layer++) {
    launch(qkv_kernel, grid, GEMM_THREADS, RA_SMEM, true, 0, layer, layer * 4, tm);
    launch(attn_kernel, layer == 0 ? 132 : 128, 512, ATT_SMEM, true, 0x3F033F03u, layer == 0, w1, maps);
    launch(wo_kernel, grid, WO_THREADS, WO_SMEM, true, layer * 4 + 1, tm);
    launch(w1_kernel, grid, GEMM_THREADS, RA_SMEM, true, 1, b1, layer * 4 + 2, tm);
    launch(w2_kernel, 128, GEMM_THREADS, W2_SMEM, true, b2, layer == 1 ? (bf16*)d_out : (bf16*)nullptr);
  }
}
```
